```python
import torch

def _softmax(x, axis=-1):
    return torch.softmax(x, dim=axis)
def _gelu(x):
    return torch.nn.functional.gelu(x, approximate="tanh")
def _silu(x):
    return torch.nn.functional.silu(x)
def _sigmoid(x):
    return torch.sigmoid(x)
def _layernorm(x, axis=-1, eps=1e-5):
    m = x.mean(dim=axis, keepdim=True)
    v = x.var(dim=axis, keepdim=True, unbiased=False)
    return (x - m) / torch.sqrt(v + eps)
def _scatter_add(tgt, idx, src, axis=0):
    return tgt.clone().index_add_(axis, idx, src)
def _segment_sum(src, seg, n):
    out = torch.zeros((n,) + src.shape[1:], dtype=src.dtype)
    return out.index_add_(0, seg, src)
def _pad(x, pw):
    flat = tuple(v for pair in reversed(pw) for v in pair)
    return torch.nn.functional.pad(x, flat)

kernel_name = 'parallel_sum__sliding_block_cached__glu_gated_swiglu__decode'

def setup_inputs():

    _w = (lambda a: (lambda t: t.to(torch.bfloat16) if t.is_floating_point() else t)(torch.as_tensor(a)))
    def _A_setup():
        B, Sq, D = 4, 1, 640
        Hq, Hkv, Sk, Dh = 32, 32, 8192, 192
        assert Hq % Hkv == 0, (Hq, Hkv)
        return {
            "x": _w((lambda *s: torch.randn(*s, dtype=torch.bfloat16) * 0.05)(B, Sq, D)),
            "k_cache": _w((lambda *s: torch.randn(*s, dtype=torch.bfloat16) * 1.6)(B, Hkv, Sk, Dh)),
            "v_cache": _w((lambda *s: torch.randn(*s, dtype=torch.bfloat16) * 0.8)(B, Hkv, Sk, Dh)),
            "wq": _w((lambda *s: torch.randn(*s, dtype=torch.bfloat16) * 1.6)(D, Hq * Dh) * (D ** -0.5)),
            "wo": _w((lambda *s: torch.randn(*s, dtype=torch.bfloat16) * 0.8)(Hq * Dh, D) * ((Hq * Dh) ** -0.5)),
        }
    _A_in = _A_setup()

    def _B_setup():
        B, S, D, F = 4, 1, 640, 1536
        return {
            "x": _w((lambda *s: torch.randn(*s, dtype=torch.bfloat16) * 0.05)(B, S, D)),
            "w1": _w((lambda *s: torch.randn(*s, dtype=torch.bfloat16) * 0.4)(D, F) * (2.0 / D) ** 0.5),
            "w3": _w((lambda *s: torch.randn(*s, dtype=torch.bfloat16) * 0.4)(D, F) * (2.0 / D) ** 0.5),
            "w2": _w((lambda *s: torch.randn(*s, dtype=torch.bfloat16) * 0.4)(F, D) * (2.0 / F) ** 0.5),
        }
    _B_in = _B_setup()

    return {
        "A_x": _A_in["x"],
        "A_k_cache": _A_in["k_cache"],
        "A_v_cache": _A_in["v_cache"],
        "A_wq": _A_in["wq"],
        "A_wo": _A_in["wo"],
        "B_x": _B_in["x"],
        "B_w1": _B_in["w1"],
        "B_w3": _B_in["w3"],
        "B_w2": _B_in["w2"],
    }

def reference(A_x, A_k_cache, A_v_cache, A_wq, A_wo, B_x, B_w1, B_w3, B_w2):
    def _A_ref(x, k_cache, v_cache, wq, wo):
        B, Sq, D = x.shape
        Hq, Dh = 32, 192
        Hkv, Sk = k_cache.shape[1], k_cache.shape[2]
        W = min(4096, max(256, Sk // 4))
        rep = Hq // Hkv
        q = (lambda x, *d: x.permute(*d))((x @ wq).reshape(B, Sq, Hq, Dh), 0, 2, 1, 3)
        k = (lambda x, n, axis: torch.repeat_interleave(x, n, dim=axis))(k_cache[:, :, Sk - W:, :], rep, axis=1)
        v = (lambda x, n, axis: torch.repeat_interleave(x, n, dim=axis))(v_cache[:, :, Sk - W:, :], rep, axis=1)
        scores = torch.einsum("bhqd,bhkd->bhqk", q, k) * (Dh ** -0.5)
        p = _softmax(scores, axis=-1)
        o = torch.einsum("bhqk,bhkd->bhqd", p, v)
        return (lambda x, *d: x.permute(*d))(o, 0, 2, 1, 3).reshape(B, Sq, Hq * Dh) @ wo

    def _B_ref(x, w1, w3, w2):
        gate = torch.einsum("bsd,df->bsf", x, w1)
        up = torch.einsum("bsd,df->bsf", x, w3)
        h = _silu(gate) * up
        out = torch.einsum("bsf,fd->bsd", h, w2)
        return out

    x = A_x
    xn = _layernorm(x, axis=-1)
    return x + _A_ref(xn, A_k_cache, A_v_cache, A_wq, A_wo) + _B_ref(xn, B_w1, B_w3, B_w2)
```

```cpp
#include <cuda_runtime.h>
#include <cuda_bf16.h>
#include <cuda.h>
#include <stdint.h>

namespace {

constexpr int D_ = 640, SK = 8192, DH = 192, WIN = 2048;
constexpr int NATT = 128, NCTA = 132;
constexpr int G = 32;
constexpr int SLOT = 12288, NSLOT = 16;
constexpr int T_KV = 5, T_TAIL = 133;
constexpr int NT_S = 12, NT_L = 6;
constexpr int BOX = 6144;
constexpr int FSLOT = 24576;
constexpr int W_PACE = 1, W_ATT = 2, W_WO = 2, W_REP = 4, W_WT = 9, W_H = 10, W_TRG = 11, W_CMB = 12, NWARP = 18;
constexpr int NREP = 2;
constexpr int NTHREADS = NWARP * 32;
constexpr int XN_PITCH = 648;
constexpr int O_PITCH = 288;
constexpr int PBLK = G * 200;
constexpr int A_PITCH = 4672;
constexpr int W_S = 6;

constexpr int INIT_N = 6;
constexpr int PACE_W = 700;
constexpr int PACE_GAP = 3072;
constexpr int D_LO = 4, D_HI = 6;
constexpr int D_END = 5;
constexpr int U_END = 12;
constexpr int U_SG = 29;
constexpr int F_THR = 125;
constexpr int STAG_UNTIL = 121;
constexpr int FFN_DEPTH = 3;
constexpr int Q_AVG = 5;

constexpr int SM_RING = 0;
constexpr int SM_XN = SM_RING + NSLOT * SLOT;
constexpr int SM_O = SM_XN + 4 * XN_PITCH * 2;
constexpr int SM_Q = SM_O + 4 * O_PITCH * 2;
constexpr int SM_QB = SM_Q + 2 * 384;
constexpr int SM_WT = SM_QB + 2 * 3072;
constexpr int SM_BAR = SM_WT + 512;
constexpr int SM_VAR = SM_BAR + (2 * NSLOT + 22) * 8;
constexpr int SM_A = SM_VAR + 48;
constexpr int SM_TOTAL = SM_A + 4 * A_PITCH;
static_assert(SM_A % 16 == 0 && SM_TOTAL <= 232448, "");

constexpr int SPIN_LIMIT = 1 << 18;
constexpr int WAIT_LIMIT = 1 << 16;
constexpr long long WAIT_CYCLES = 1ll << 30;

struct Scratch {
    float qmb[NATT * 4 * DH];
    float pmb[NATT * PBLK];
    float amb[36 * 4 * DH];
    unsigned prog[2 * 32];
    unsigned fin[2 * NATT * 32];
    unsigned rep[2 * 4 * NREP * 7 * 32];
    unsigned init[2 * 32];
    unsigned epoch[160];
};
__device__ __align__(128) Scratch g_s;

__device__ __forceinline__ uint32_t smem_u32(const void* p) { return (uint32_t)__cvta_generic_to_shared(p); }
__device__ __forceinline__ void mbar_init(uint32_t a, uint32_t c) {
    asm volatile("mbarrier.init.shared::cta.b64 [%0], %1;" ::"r"(a), "r"(c) : "memory");
}
__device__ __forceinline__ void mbar_expect(uint32_t a, uint32_t bytes) {
    asm volatile("mbarrier.arrive.expect_tx.shared::cta.b64 _, [%0], %1;" ::"r"(a), "r"(bytes) : "memory");
}
__device__ __forceinline__ void mbar_arrive(uint32_t a, uint32_t cnt) {
    asm volatile("mbarrier.arrive.shared::cta.b64 _, [%0], %1;" ::"r"(a), "r"(cnt) : "memory");
}
__device__ __forceinline__ bool mbar_test(uint32_t a, uint32_t parity) {
    uint32_t ok;
    asm volatile("{.reg .pred p; mbarrier.test_wait.parity.shared::cta.b64 p, [%1], %2; selp.u32 %0,1,0,p;}"
                 : "=r"(ok) : "r"(a), "r"(parity) : "memory");
    return ok;
}
__device__ __forceinline__ void mbar_wait(uint32_t a, uint32_t parity) {
    asm volatile(
        "{.reg .pred p, q; .reg .u32 n; mov.u32 n, 0;\n"
        "WAIT_%=: mbarrier.try_wait.parity.shared::cta.b64 p, [%0], %1;\n"
        "@p bra DONE_%=;\n"
        "add.u32 n, n, 1; setp.lt.u32 q, n, %2;\n"
        "@q bra WAIT_%=;\n"
        "DONE_%=:}" ::"r"(a), "r"(parity), "n"(WAIT_LIMIT) : "memory");
}
__device__ __forceinline__ void bulk_load(uint32_t dst, const void* src, uint32_t bytes, uint32_t mbar, uint64_t pol) {
    asm volatile("cp.async.bulk.shared::cluster.global.mbarrier::complete_tx::bytes.L2::cache_hint [%0], [%1], %2, [%3], %4;"
                 ::"r"(dst), "l"(src), "r"(bytes), "r"(mbar), "l"(pol) : "memory");
}
__device__ __forceinline__ void bulk_load(uint32_t dst, const void* src, uint32_t bytes, uint32_t mbar) {
    asm volatile("cp.async.bulk.shared::cluster.global.mbarrier::complete_tx::bytes [%0], [%1], %2, [%3];"
                 ::"r"(dst), "l"(src), "r"(bytes), "r"(mbar) : "memory");
}
__device__ __forceinline__ void tma3(uint32_t dst, const CUtensorMap* map, int c1, int c2, uint32_t mbar, uint64_t pol) {
    asm volatile("cp.async.bulk.tensor.3d.shared::cluster.global.mbarrier::complete_tx::bytes.L2::cache_hint [%0], [%1, {%2, %3, %4}], [%5], %6;"
                 ::"r"(dst), "l"((uint64_t)map), "r"(0), "r"(c1), "r"(c2), "r"(mbar), "l"(pol) : "memory");
}
__device__ __forceinline__ void tma2(uint32_t dst, const CUtensorMap* map, int c0, int c1, uint32_t mbar) {
    asm volatile("cp.async.bulk.tensor.2d.shared::cluster.global.mbarrier::complete_tx::bytes [%0], [%1, {%2, %3}], [%4];"
                 ::"r"(dst), "l"((uint64_t)map), "r"(c0), "r"(c1), "r"(mbar) : "memory");
}
__device__ __forceinline__ void prefetch_map(const CUtensorMap* map) {
    asm volatile("prefetch.tensormap [%0];" ::"l"((uint64_t)map) : "memory");
}
__device__ __forceinline__ void ldsm4(uint32_t (&r)[4], uint32_t a) {
    asm volatile("ldmatrix.sync.aligned.m8n8.x4.shared.b16 {%0,%1,%2,%3}, [%4];"
                 : "=r"(r[0]), "=r"(r[1]), "=r"(r[2]), "=r"(r[3]) : "r"(a) : "memory");
}
__device__ __forceinline__ void ldsm4t(uint32_t (&r)[4], uint32_t a) {
    asm volatile("ldmatrix.sync.aligned.m8n8.x4.trans.shared.b16 {%0,%1,%2,%3}, [%4];"
                 : "=r"(r[0]), "=r"(r[1]), "=r"(r[2]), "=r"(r[3]) : "r"(a) : "memory");
}
__device__ __forceinline__ void mma16816(float (&c)[4], const uint32_t (&a)[4], uint32_t b0, uint32_t b1) {
    asm volatile("mma.sync.aligned.m16n8k16.row.col.f32.bf16.bf16.f32 {%0,%1,%2,%3}, {%4,%5,%6,%7}, {%8,%9}, {%0,%1,%2,%3};"
                 : "+f"(c[0]), "+f"(c[1]), "+f"(c[2]), "+f"(c[3])
                 : "r"(a[0]), "r"(a[1]), "r"(a[2]), "r"(a[3]), "r"(b0), "r"(b1));
}
__device__ __forceinline__ float bf16r(float v) { return __bfloat162float(__float2bfloat16_rn(v)); }
__device__ __forceinline__ uint32_t pack_bf16(float lo, float hi) {
    __nv_bfloat162 t = __floats2bfloat162_rn(lo, hi);
    return *reinterpret_cast<uint32_t*>(&t);
}
__device__ __forceinline__ void st_tag(float* p, float v, uint32_t tag) {
    asm volatile("st.relaxed.gpu.global.b32 [%0], %1;" ::"l"(p), "r"((__float_as_uint(v) & ~1u) | tag) : "memory");
}
__device__ __forceinline__ float untag(uint32_t w) { return __uint_as_float(w & ~1u); }
__device__ __forceinline__ uint32_t chk(uint32_t acc, uint32_t w, uint32_t tag) {
    uint32_t r;
    asm("lop3.b32 %0, %1, %2, %3, 0xF6;" : "=r"(r) : "r"(acc), "r"(w), "r"(tag));
    return r;
}
__device__ __forceinline__ uint4 ld_mb4(const void* p) {
    uint4 v;
    asm volatile("ld.relaxed.gpu.global.v4.b32 {%0,%1,%2,%3}, [%4];"
                 : "=r"(v.x), "=r"(v.y), "=r"(v.z), "=r"(v.w) : "l"(p) : "memory");
    return v;
}
__device__ __forceinline__ uint2 ld_mb2(const void* p) {
    uint2 v;
    asm volatile("ld.relaxed.gpu.global.v2.b32 {%0,%1}, [%2];" : "=r"(v.x), "=r"(v.y) : "l"(p) : "memory");
    return v;
}
__device__ __forceinline__ void red_add(unsigned* p, uint32_t v) {
    asm volatile("red.relaxed.gpu.global.add.u32 [%0], %1;" ::"l"(p), "r"(v) : "memory");
}
__device__ __forceinline__ uint32_t ld_mb1(const void* p) {
    uint32_t v;
    asm volatile("ld.relaxed.gpu.global.b32 %0, [%1];" : "=r"(v) : "l"(p) : "memory");
    return v;
}

template <int NCG>
__device__ __forceinline__ uint32_t wt_addr(uint32_t box, int lane, int r0, int cg, int mt) {
    int mat = lane >> 3;
    int r = r0 + (lane & 7) + ((mat >> 1) << 3);
    int ch = 2 * mt + (mat & 1);
    int line = r * NCG + cg;
    return box + line * 128 + ((ch ^ (line & 7)) << 4);
}

struct Params {
    const __nv_bfloat16* x;
    const __nv_bfloat16* k;
    const __nv_bfloat16* v;
    const __nv_bfloat16* wq;
    __nv_bfloat16* out;
    Scratch* s;
};

__device__ __forceinline__ void out_red(__nv_bfloat16* dst, float lo, float hi) {
    asm volatile("red.relaxed.gpu.global.add.noftz.bf16x2 [%0], %1;" ::"l"(dst), "r"(pack_bf16(lo, hi)) : "memory");
}
__device__ __forceinline__ uint32_t ld_acq(const void* p) {
    uint32_t v;
    asm volatile("ld.acquire.gpu.global.b32 %0, [%1];" : "=r"(v) : "l"(p) : "memory");
    return v;
}
struct Strip { int rt, cb; };
__device__ __forceinline__ Strip strip_role() {
    int c;
    asm volatile("mov.u32 %0, %%ctaid.x;" : "=r"(c));
    const int er = c - (c >> 5) * 4;
    Strip s;
    s.rt = c < NATT ? er / 40 : 2;
    s.cb = c < NATT ? er % 40 : 32 + 2 * (c & 3);
    return s;
}
__device__ __forceinline__ void strip_load(uint32_t dst, const CUtensorMap* wo, const CUtensorMap* w2, int q, int cb,
                                           uint32_t bar) {
    if (q < 28) tma2(dst, wo, 16 * cb, DH * (q + q / 7), bar);
    else tma2(dst, w2, 16 * cb, DH * (q - 28), bar);
}

__global__ void __launch_bounds__(NTHREADS, 1)
fused_decode_kernel(const Params p, const __grid_constant__ CUtensorMap m_wq, const __grid_constant__ CUtensorMap m_wo,
                    const __grid_constant__ CUtensorMap m_w1, const __grid_constant__ CUtensorMap m_w3,
                    const __grid_constant__ CUtensorMap m_wos, const __grid_constant__ CUtensorMap m_w2s) {
    extern __shared__ __align__(1024) unsigned char smem[];
    const uint32_t sb = smem_u32(smem);
    uint32_t trips = 0;
    asm volatile("{.reg .pred p;\n"
                 "setp.ne.u32 p, %2, 64; @p bra PF_DONE;\n"
                 "PF_GO: cp.async.bulk.prefetch.L2.global [%1], 12288;\n"
                 "add.u32 %0, %0, 1; setp.gt.u32 p, %3, 0x7ffffff0; @p bra PF_GO;\n"
                 "PF_DONE:}"
                 : "+r"(trips)
                 : "l"(p.wq + (size_t)(160 * (blockIdx.x & 3) + (blockIdx.x >> 2)) * 6144), "r"(threadIdx.x), "r"(blockIdx.x)
                 : "memory");
    const int tid = threadIdx.x + (trips >> 1), warp = tid >> 5, lane = tid & 31;
    const int c = blockIdx.x;
    const bool is_att = c < NATT;
    const int h = c >> 2, j = c & 3;
    const int grp = c / G, src = c % G;
    const bool late = is_att && (h & 7) == 7;
    const int pf = late ? h * 4 : c, np = late ? 4 : 1;
    const uint32_t bar_full = sb + SM_BAR, bar_empty = bar_full + NSLOT * 8;
    const uint32_t bar_sig = bar_empty + NSLOT * 8, bar_done = bar_sig + 32, bar_late = bar_done + 8;
    const uint32_t bar_h = bar_late + 8, bar_o = bar_h + 8, bar_q0 = bar_o + 8, bar_own = bar_q0 + 16;
    const uint32_t bar_sga = bar_own + 8, bar_wt = bar_sga + 32, bar_sg = bar_wt + 32, bar_d0 = bar_sg + 8, bar_a = bar_d0 + 8;
    volatile int* s_var = reinterpret_cast<volatile int*>(smem + SM_VAR);
    volatile unsigned long long* s_win = reinterpret_cast<volatile unsigned long long*>(smem + SM_VAR + 8);

    uint2 raw[5];
    if ((warp & ~3) == 4) {
        const uint2* xp = reinterpret_cast<const uint2*>(p.x + (warp - 4) * D_) + lane;
#pragma unroll
        for (int i = 0; i < 5; i++)
            asm volatile("ld.global.nc.v2.u32 {%0,%1}, [%2];" : "=r"(raw[i].x), "=r"(raw[i].y) : "l"(xp + 32 * i));
    }
    uint32_t epoch0 = 0;
    if (tid == W_PACE * 32) epoch0 = ld_mb1(p.s->epoch + c);
    uint64_t pol;
    asm volatile("createpolicy.fractional.L2::evict_first.b64 %0, 1.0;" : "=l"(pol));
    const size_t kv_off = ((size_t)(grp * (G / 4)) * SK + (SK - WIN) + src * 64) * DH;
    if (tid == 0 && is_att) {
#pragma unroll
        for (int t = 0; t < INIT_N; t++) {
            mbar_init(bar_full + t * 8, 1);
            mbar_expect(bar_full + t * 8, SLOT);
            if (t < T_KV) tma3(sb + t * SLOT, &m_wq, 3 * h, 160 * j + 32 * t, bar_full + t * 8, pol);
            else bulk_load(sb + t * SLOT, (const char*)(p.k + kv_off) + (t - T_KV) * SLOT, SLOT, bar_full + t * 8, pol);
        }
    }

    if (tid < 32) {
        const char* kp = (const char*)(p.k + kv_off);
        const char* vp = (const char*)(p.v + kv_off);
        if (lane == 0) {
            for (int s = is_att ? INIT_N : 0; s < NSLOT; s++) mbar_init(bar_full + s * 8, 1);
#pragma unroll
            for (int s = 0; s < NSLOT; s++) mbar_init(bar_empty + s * 8, is_att ? 6 : 8);
#pragma unroll
            for (int s = 0; s < 7; s++) mbar_init(bar_sig + s * 8, s == 4 ? 2 : 1);
            mbar_init(bar_o, 24);
#pragma unroll
            for (int s = 0; s < 13; s++) mbar_init(bar_q0 + s * 8, 1);
            mbar_init(bar_a, 6);
            asm volatile("fence.proxy.async.shared::cta;" ::: "memory");
            s_var[1] = 0;
            *s_win = 0;
            s_var[4] = 0;
            s_var[5] = 0;
        }
        __syncwarp();
        asm volatile("bar.arrive 0, %0;" ::"n"(NTHREADS) : "memory");
        asm volatile("bar.arrive 4, 64;" ::: "memory");
        if (lane == 0) {
            if (is_att) {
                int issued = INIT_N, landed = 0;
                const long long t0 = clock64();
                const int ntile = T_TAIL + (late ? NT_L : NT_S);
                const Strip sr = strip_role();
                while (issued < ntile) {
                    if (mbar_test(bar_full + (landed & 15) * 8, (landed >> 4) & 1)) s_var[1] = ++landed;
                    else if (clock64() - t0 > WAIT_CYCLES) break;
                    const unsigned long long wv = *s_win;
                    int win = (uint32_t)wv & 0xffff;
                    win += (min((uint32_t)clock() - (uint32_t)(wv >> 32), 2u * PACE_GAP) * ((uint32_t)wv >> 16)) >> 12;
                    if (issued < STAG_UNTIL) win += 128 - grp * 64;
                    const int target = issued < T_TAIL ? min(max(win >> 7, landed + D_LO), landed + D_HI)
                                                       : landed + (late ? D_END : U_END - max(T_TAIL - landed, 0));
                    const int need = issued < T_TAIL ? (((issued - T_KV) & 1) ? -1 : issued + 1) : issued;
                    if (need < target &&
                        (issued < NSLOT || mbar_test(bar_empty + (issued & 15) * 8, ((issued >> 4) - 1) & 1))) {
                        const uint32_t dst = sb + (issued & 15) * SLOT, bar = bar_full + (issued & 15) * 8;
                        if (issued < T_TAIL) {
                            const int r = issued - T_KV, u = r >> 2;
                            const size_t o = (size_t)((u & 3) * 32 + (u >> 2)) * (SK * DH * 2) + (r & 1) * SLOT;
                            mbar_expect(bar, SLOT);
                            bulk_load(dst, ((r & 2) ? vp : kp) + o, SLOT, bar, pol);
                        } else if (late) {
                            mbar_expect(bar, 10240);
                            tma3(dst, &m_wo, 5 * j, 192 * h + 32 * (issued - T_TAIL), bar, pol);
                        } else {
                            mbar_expect(bar, BOX);
                            strip_load(dst, &m_wos, &m_w2s, 12 * sr.rt + issued - T_TAIL, sr.cb, bar);
                        }
                        issued++;
                    }
                }
                s_var[1] = T_TAIL + NT_L;
            } else {
#pragma unroll 1
                for (int t = 0; t < 40; t++) {
                    if (t >= FFN_DEPTH) mbar_wait(bar_full + ((t - FFN_DEPTH) & 7) * 8, ((t - FFN_DEPTH) >> 3) & 1);
                    if (t >= 8) mbar_wait(bar_empty + (t & 7) * 8, ((t >> 3) - 1) & 1);
                    const uint32_t dst = sb + (t & 7) * FSLOT, bar = bar_full + (t & 7) * 8;
                    mbar_expect(bar, FSLOT);
                    tma3(dst, &m_w1, 6 * j, 16 * t, bar, pol);
                    tma3(dst + 6144, &m_w1, 6 * j + 3, 16 * t, bar, pol);
                    tma3(dst + 12288, &m_w3, 6 * j, 16 * t, bar, pol);
                    tma3(dst + 18432, &m_w3, 6 * j + 3, 16 * t, bar, pol);
                }
                for (int s = 0; s < 8; s++) mbar_wait(bar_empty + s * 8, 0);
#pragma unroll 1
                for (int ch = 0; ch < 4; ch++) {
                    if (ch) mbar_wait(bar_full + (7 + ch) * 8, 0);
                    mbar_expect(bar_full + (8 + ch) * 8, 6 * BOX);
#pragma unroll 1
                    for (int i = 0; i < 6; i++)
                        strip_load(sb + (ch * 6 + i) * BOX, &m_wos, &m_w2s, 24 + (ch & 1) * 6 + i, 32 + 2 * j + (ch >> 1), bar_full + (8 + ch) * 8);
                }
            }
        }
        return;
    }
    if (warp == W_PACE) {
        const uint32_t epoch = epoch0;
        if (lane == 0) s_var[0] = epoch;
        __syncwarp();
        asm volatile("bar.arrive 0, %0;" ::"n"(NTHREADS) : "memory");
        asm volatile("bar.sync 4, 64;" ::: "memory");
        if (lane == 0) p.s->epoch[c] = epoch + 1;
        if (lane == 0 && is_att) {
            unsigned* ctr = p.s->prog + (epoch & 1) * 32;
            if (c == 0) p.s->prog[((epoch & 1) ^ 1) * 32] = p.s->init[((epoch & 1) ^ 1) * 32] = 0;
            p.s->fin[(((epoch & 1) ^ 1) * NATT + c) * 32] = 0;
            if (c < 4 * NREP) p.s->rep[(((epoch & 1) ^ 1) * 4 * NREP + c) * 7 * 32] = 0;
            int rep = 0, tot = 0, prev = 0, it = 0;
            float rate = 530.f;
            uint32_t t_prev = clock(), t_next = t_prev + ((c * 79) & 127) * (PACE_GAP / 128);
            while (tot + PACE_W < T_TAIL * 128 && rep < T_TAIL && ++it < SPIN_LIMIT) {
                while ((int)(clock() - t_next) < 0) __nanosleep(20);
                const int l = s_var[1];
                const uint32_t t1 = clock();
                tot = (int)(atomicAdd(ctr, l - rep) + (l - rep));
                const uint32_t t2 = clock();
                rep = l;
                t_next += PACE_GAP;
                if ((int)(t2 - t_next) > 0) t_next = t2;
                const uint32_t tm = t1 + ((t2 - t1) >> 1);
                rate += 0.05f * (__fdividef((float)((tot - prev) << 12), (float)(tm - t_prev)) - rate);
                prev = tot;
                t_prev = tm;
                *s_win = ((unsigned long long)(tm - PACE_GAP / 2) << 32) | ((uint32_t)rate << 16) | (uint32_t)(tot + PACE_W);
            }
        }
        return;
    }

    const int g = lane >> 2, tig = lane & 3;
    __nv_bfloat16* xn_s = reinterpret_cast<__nv_bfloat16*>(smem + SM_XN);

    if (warp >= 4 && warp < 8) {
        const int b = warp - 4;
        float xv[20];
#pragma unroll
        for (int i = 0; i < 5; i++) {
            xv[4 * i + 0] = __uint_as_float(raw[i].x << 16);
            xv[4 * i + 1] = __uint_as_float(raw[i].x & 0xffff0000u);
            xv[4 * i + 2] = __uint_as_float(raw[i].y << 16);
            xv[4 * i + 3] = __uint_as_float(raw[i].y & 0xffff0000u);
        }
        float s = 0.f;
#pragma unroll
        for (int i = 0; i < 20; i++) s += xv[i];
#pragma unroll
        for (int o = 16; o; o >>= 1) s += __shfl_xor_sync(~0u, s, o);
        const float mean = s * (1.f / D_);
        float vs = 0.f;
#pragma unroll
        for (int i = 0; i < 20; i++) { float d = xv[i] - mean; vs += d * d; }
#pragma unroll
        for (int o = 16; o; o >>= 1) vs += __shfl_xor_sync(~0u, vs, o);
        const float mb = bf16r(mean);
        const float den = bf16r(sqrtf(bf16r(bf16r(vs * (1.f / D_)) + 1e-5f)));
        const float rden = 1.f / den;
#pragma unroll
        for (int i = 0; i < 5; i++) {
            uint2 o;
            o.x = pack_bf16(bf16r(xv[4 * i + 0] - mb) * rden, bf16r(xv[4 * i + 1] - mb) * rden);
            o.y = pack_bf16(bf16r(xv[4 * i + 2] - mb) * rden, bf16r(xv[4 * i + 3] - mb) * rden);
            *reinterpret_cast<uint2*>(xn_s + b * XN_PITCH + (lane + 32 * i) * 4) = o;
        }
    }
    asm volatile("bar.sync 0, %0;" ::"n"(NTHREADS) : "memory");
    const uint32_t epoch = s_var[0];
    const uint32_t tag = (epoch & 1) ^ 1;
    const uint32_t* xn_w = reinterpret_cast<const uint32_t*>(xn_s + (g & 3) * XN_PITCH) + tig;
    const int hi = tig >> 1, pr = tig & 1;

    if (!is_att) {
        const int w = warp - 2;
        if (warp == W_CMB + 1) {
            for (int i = lane; i < D_ / 8; i += 32)
                reinterpret_cast<uint4*>(p.out + j * D_)[i] = __ldg(reinterpret_cast<const uint4*>(p.x + j * D_) + i);
            __syncwarp();
            if (lane == 0) {
                __threadfence();
                red_add(p.s->init + (epoch & 1) * 32, 1);
            }
        } else if (warp == W_CMB) {
            if (lane == 0) {
                int it = 0;
                while (ld_acq(p.s->init + (epoch & 1) * 32) < 4 && ++it < SPIN_LIMIT) __nanosleep(200);
                mbar_arrive(bar_h, 1);
                while (ld_mb1(p.s->prog + (epoch & 1) * 32) < F_THR * 128 && ++it < SPIN_LIMIT) __nanosleep(500);
                mbar_arrive(bar_sg, 1);
            }
            __syncwarp();
        } else if (w < 8) {
            float ga[3][4], ua[3][4];
            uint32_t aoff[3];
#pragma unroll
            for (int i = 0; i < 3; i++) {
                ga[i][0] = ga[i][1] = ga[i][2] = ga[i][3] = 0.f;
                ua[i][0] = ua[i][1] = ua[i][2] = ua[i][3] = 0.f;
                const int mtg = w * 3 + i, cg6 = mtg >> 2, half = cg6 >= 3;
                aoff[i] = wt_addr<3>(half * 6144, lane, 0, cg6 - 3 * half, mtg & 3);
            }
            for (int t = 0; t < 40; t++) {
                const int s = t & 7;
                const uint32_t b0 = xn_w[t * 8], b1 = xn_w[t * 8 + 4];
                mbar_wait(bar_full + s * 8, (t >> 3) & 1);
                const uint32_t base = sb + s * FSLOT;
#pragma unroll
                for (int i = 0; i < 3; i++) {
                    uint32_t a[4], b[4];
                    ldsm4t(a, base + aoff[i]);
                    ldsm4t(b, base + aoff[i] + 12288);
                    mma16816(ga[i], a, b0, b1);
                    mma16816(ua[i], b, b0, b1);
                }
                __syncwarp();
                if (lane == 0) mbar_arrive(bar_empty + s * 8, 1);
            }
#pragma unroll
            for (int i = 0; i < 3; i++) {
#pragma unroll
                for (int e = 0; e < 2; e++) {
                    const float gv = bf16r(hi ? ga[i][2 + e] : ga[i][e]), uv = bf16r(hi ? ua[i][2 + e] : ua[i][e]);
                    const float si = bf16r(gv / (1.f + __expf(-gv)));
                    const int blk = w * 3 + i, up = blk >= 12;
                    st_tag(p.s->amb + ((28 + 2 * j + up) * 4 + 2 * pr + e) * DH + (blk - 12 * up) * 16 + hi * 8 + g, bf16r(si * uv), tag);
                }
            }
        }
        if (warp < W_S) return;
    } else if (warp >= W_CMB) {
        const int w = warp - W_CMB;
        {
            float acc[2][4];
#pragma unroll
            for (int i = 0; i < 2; i++) acc[i][0] = acc[i][1] = acc[i][2] = acc[i][3] = 0.f;
#pragma unroll
            for (int t = 0; t < T_KV; t++) {
                mbar_wait(bar_full + t * 8, 0);
#pragma unroll
                for (int ks = 0; ks < 2; ks++) {
                    const int kk = 160 * j + 32 * t + 16 * ks;
                    const uint32_t b0 = xn_w[kk >> 1], b1 = xn_w[(kk >> 1) + 4];
#pragma unroll
                    for (int i = 0; i < 2; i++) {
                        const int mtg = w * 2 + i;
                        uint32_t a[4];
                        ldsm4t(a, wt_addr<3>(sb + t * SLOT, lane, ks * 16, mtg >> 2, mtg & 3));
                        mma16816(acc[i], a, b0, b1);
                    }
                }
                __syncwarp();
                if (lane == 0) mbar_arrive(bar_empty + t * 8, 1);
            }
#pragma unroll
            for (int i = 0; i < 2; i++) {
                float* dst = p.s->qmb + ((h * 4 + 2 * pr) * 4 + j) * DH + (w * 2 + i) * 16 + hi * 8 + g;
                st_tag(dst, hi ? acc[i][2] : acc[i][0], tag);
                st_tag(dst + 4 * DH, hi ? acc[i][3] : acc[i][1], tag);
            }
            asm volatile("bar.arrive 2, 256;" ::: "memory");
        }
        constexpr int NL = G / 4;
        const int q4 = lane >> 3, wd = lane & 7;
        uint32_t* os = reinterpret_cast<uint32_t*>(smem + SM_O) + 16 * w + 8 * (wd & 1) + 2 * (wd >> 2) + ((wd >> 1) & 1);
#pragma unroll 1
        for (int b = 0; b < np; b++) {
            const float* pd = p.s->pmb + (pf + b) * PBLK + w * (G * 32) + lane * 4;
            asm volatile("" : "+l"(pd));
            mbar_wait(bar_sig + b * 8, 0);
            uint32_t o01, o23;
            for (int it = 0; it < SPIN_LIMIT; it++) {
                uint4 d[NL];
#pragma unroll
                for (int i = 0; i < NL; i++) d[i] = ld_mb4(pd + i * 128);
                mbar_wait(bar_wt + b * 8, 0);
                const float4* ws = reinterpret_cast<const float4*>(smem + SM_WT + b * 128 + q4 * 32);
                const float4 w0 = ws[0], w1 = ws[1];
                const float wi[NL] = {w0.x, w0.y, w0.z, w0.w, w1.x, w1.y, w1.z, w1.w};
                float o[4] = {0.f, 0.f, 0.f, 0.f};
#pragma unroll
                for (int i = 0; i < NL; i++) {
                    o[0] += wi[i] * __uint_as_float(d[i].x);
                    o[1] += wi[i] * __uint_as_float(d[i].y);
                    o[2] += wi[i] * __uint_as_float(d[i].z);
                    o[3] += wi[i] * __uint_as_float(d[i].w);
                }
                const uint32_t tg = tag | (__float_as_uint(o[0]) & ~1u);
#pragma unroll
                for (int e = 0; e < 4; e++) o[e] += __shfl_xor_sync(~0u, o[e], 8);
                uint32_t b0 = 0, b1 = 0;
#pragma unroll
                for (int i = 0; i < NL; i++) { b0 = chk(b0, d[i].x, tg); b1 = chk(b1, d[i].y, tg); }
                const uint32_t tg2 = tag | (__float_as_uint(o[0]) & ~1u);
#pragma unroll
                for (int e = 0; e < 4; e++) o[e] += __shfl_xor_sync(~0u, o[e], 16);
#pragma unroll
                for (int i = 0; i < NL; i++) { b0 = chk(b0, d[i].z, tg2); b1 = chk(b1, d[i].w, tg2); }
                o01 = pack_bf16(o[0], o[1]);
                o23 = pack_bf16(o[2], o[3]);
                if (late && lane < 8) {
                    os[b * (O_PITCH / 2)] = o01;
                    os[b * (O_PITCH / 2) + 4] = o23;
                }
                if (!__any_sync(~0u, (b0 | b1) & 1)) break;
            }
            if (late) {
                __syncwarp();
                if (lane == 0) mbar_arrive(bar_o, 1);
            } else if (lane < 8) {
                float* dst = p.s->amb + ((h - (h >> 3)) * 4 + j) * DH + 32 * w + 4 * wd;
                asm volatile("st.relaxed.gpu.global.v4.b32 [%0], {%1,%2,%3,%4};" ::"l"(dst), "r"((o01 << 16) | tag),
                             "r"((o01 & 0xffff0000u) | tag), "r"((o23 << 16) | tag), "r"((o23 & 0xffff0000u) | tag) : "memory");
            }
        }
        if (late) return;
    } else {
    const int r8 = lane & 7, mat = lane >> 3;
    if (warp == W_H) {
        if (lane == 0) {
            prefetch_map(late ? &m_wo : &m_wos);
            if (!late) prefetch_map(&m_w2s);
            mbar_wait(bar_late, 0);
            for (int it = 0; ld_acq(p.s->init + (epoch & 1) * 32) < 4 && it < SPIN_LIMIT; it++) {}
            mbar_arrive(bar_h, 1);
        }
        __syncwarp();
    }
    if (warp == W_WT) {
#pragma unroll 1
        for (int b = 0; b < np; b++) {
            const float* pm = p.s->pmb + (pf + b) * PBLK + G * DH + lane * 8;
            mbar_wait(bar_sga + b * 8, 0);
            uint2 ml;
            for (int it = 0; it < SPIN_LIMIT; it++) {
                ml = ld_mb2(pm);
                if (!__any_sync(~0u, ((ml.x ^ tag) | (ml.y ^ tag)) & 1)) break;
            }
            const float mu = untag(ml.x);
            const int key = __float_as_int(mu);
            const int kmax = __reduce_max_sync(~0u, key ^ ((key >> 31) & 0x7fffffff));
            const float wt = __expf(mu - __int_as_float(kmax ^ ((kmax >> 31) & 0x7fffffff)));
            float L = wt * untag(ml.y);
#pragma unroll
            for (int sft = 16; sft; sft >>= 1) L += __shfl_xor_sync(~0u, L, sft);
            reinterpret_cast<float*>(smem + SM_WT)[b * 32 + (lane & 3) * 8 + (lane >> 2)] = __fdividef(wt, L);
            __syncwarp();
            if (lane == 0) mbar_arrive(bar_wt + b * 8, 1);
        }
    }
    if (warp == W_TRG) {
        if (lane == 0) {
            mbar_wait(bar_own, 0);
            for (int b = 0; b < np; b++) {
                unsigned* fin = p.s->fin + ((epoch & 1) * NATT + pf + b) * 32;
                bool sa = false;
                for (int it = 0; it < SPIN_LIMIT; it++) {
                    const unsigned v = atomicAdd(fin, 0);
                    if (!sa && v >= (G << 8)) {
                        if (b < 3 || atomicExch((int*)s_var + 5, 1) == 0) mbar_arrive(bar_sga + b * 8, 1);
                        sa = true;
                    }
                    if ((v & 0xff) >= G || (b == 3 && s_var[4])) break;
                }
                if (b < 3 || atomicExch((int*)s_var + 4, 1) == 0) mbar_arrive(bar_sig + b * 8, 1);
            }
        }
        __syncwarp();
    }
    if (warp >= W_REP && warp < W_REP + NREP && (src >> 2) == G / 4 - 1) {
        if (lane == 0) {
            mbar_wait(bar_sig + 8, 0);
            unsigned* fin = p.s->rep + (((epoch & 1) * 4 + grp) * NREP + warp - W_REP) * 7 * 32;
            bool sa = false;
            for (int it = 0; it < SPIN_LIMIT; it++) {
                const unsigned v = atomicAdd(fin, 0);
                if (!sa && v >= (G << 8)) {
                    if (atomicExch((int*)s_var + 5, 1) == 0) mbar_arrive(bar_sga + 24, 1);
                    sa = true;
                }
                if ((v & 0xff) >= G || s_var[4]) break;
            }
            if (atomicExch((int*)s_var + 4, 1) == 0) mbar_arrive(bar_sig + 24, 1);
        }
        __syncwarp();
    }
    if (warp < W_ATT + 2) {
        const int uw = warp - W_ATT;
        uint32_t* qs = reinterpret_cast<uint32_t*>(smem + SM_Q) + uw * 96;
        uint32_t koff[4], voff[4];
#pragma unroll
        for (int i = 0; i < 4; i++) {
            koff[i] = (r8 + ((mat & 1) << 3)) * 384 + (((2 * i + (mat >> 1)) ^ r8) << 4);
            voff[i] = (r8 + ((mat >> 1) << 3)) * 384 + (((2 * i + (mat & 1)) ^ r8) << 4);
        }
        const bool diag = tig == (g >> 1);
        asm volatile("bar.sync 2, 256;" ::: "memory");
        for (int it = 0; (int)(*s_win & 0xffff) < Q_AVG * 128 + PACE_W && it < SPIN_LIMIT; it++) __nanosleep(64);
        const uint32_t bar_q = bar_q0 + uw * 8;
        uint32_t qphase = 0;
        if (lane == 0) {
            mbar_expect(bar_q, 3072);
            bulk_load(sb + SM_QB + uw * 3072, p.s->qmb + (grp * G + uw) * 4 * DH, 3072, bar_q);
        }
#pragma unroll 1
        for (int u = uw; u < G; u += 2) {
            const int pair = grp * G + u;
            uint32_t pb[8];
            float m, l;
            {
                uint2 qv[4][3];
                for (int it = 0; it < SPIN_LIMIT; it++) {
                    mbar_wait(bar_q, qphase);
                    qphase ^= 1;
                    uint32_t bad = 0;
#pragma unroll
                    for (int i = 0; i < 4; i++)
#pragma unroll
                        for (int k = 0; k < 3; k++) {
                            qv[i][k] = *reinterpret_cast<const uint2*>(smem + SM_QB + uw * 3072 + i * 768 + k * 256 + lane * 8);
                        }
#pragma unroll
                    for (int i = 0; i < 4; i++)
#pragma unroll
                        for (int k = 0; k < 3; k++) bad = chk(chk(bad, qv[i][k].x, tag), qv[i][k].y, tag);
                    const bool ok = !__any_sync(~0u, bad & 1);
                    if (lane == 0 && (!ok || u + 2 < G)) {
                        mbar_expect(bar_q, 3072);
                        bulk_load(sb + SM_QB + uw * 3072, p.s->qmb + (pair + (ok ? 2 : 0)) * 4 * DH, 3072, bar_q);
                    }
                    if (ok) break;
                }
#pragma unroll
                for (int k = 0; k < 3; k++)
                    qs[lane + 32 * k] = pack_bf16((untag(qv[0][k].x) + untag(qv[1][k].x)) + (untag(qv[2][k].x) + untag(qv[3][k].x)),
                                                  (untag(qv[0][k].y) + untag(qv[1][k].y)) + (untag(qv[2][k].y) + untag(qv[3][k].y)));
                __syncwarp();
                uint32_t qf[24];
#pragma unroll
                for (int i = 0; i < 24; i++) qf[i] = qs[((i & 24) + ((i & 7) ^ g)) * 4 + tig];
                __syncwarp();
                float sc[8];
#pragma unroll
                for (int i = 0; i < 2; i++) {
                    const int t = T_KV + 4 * u + i, s = t & 15;
                    mbar_wait(bar_full + s * 8, (t >> 4) & 1);
                    const uint32_t base = sb + s * SLOT;
                    float acc[4][4];
#pragma unroll
                    for (int k = 0; k < 4; k++) acc[k][0] = acc[k][1] = acc[k][2] = acc[k][3] = 0.f;
#pragma unroll
                    for (int st = 0; st < 12; st++) {
#pragma unroll
                        for (int blk = 0; blk < 2; blk++) {
                            uint32_t a[4];
                            ldsm4(a, base + koff[st & 3] + (st >> 2) * 128 + blk * 6144);
                            mma16816(acc[blk * 2 + (st & 1)], a, qf[2 * st], qf[2 * st + 1]);
                        }
                    }
                    __syncwarp();
                    if (lane == 0) mbar_arrive(bar_empty + s * 8, 6);
                    const float scale = 0.07216878364870322f;
#pragma unroll
                    for (int blk = 0; blk < 2; blk++) {
                        const float s0 = (g & 1) ? acc[2 * blk][1] + acc[2 * blk + 1][1] : acc[2 * blk][0] + acc[2 * blk + 1][0];
                        const float s1 = (g & 1) ? acc[2 * blk][3] + acc[2 * blk + 1][3] : acc[2 * blk][2] + acc[2 * blk + 1][2];
                        sc[i * 4 + blk * 2] = diag ? bf16r(bf16r(s0) * scale) : -INFINITY;
                        sc[i * 4 + blk * 2 + 1] = diag ? bf16r(bf16r(s1) * scale) : -INFINITY;
                    }
                }
                m = -3.0e38f;
#pragma unroll
                for (int i = 0; i < 8; i++) m = fmaxf(m, sc[i]);
#pragma unroll
                for (int o = 16; o; o >>= 1) m = fmaxf(m, __shfl_xor_sync(~0u, m, o));
                l = 0.f;
#pragma unroll
                for (int i = 0; i < 8; i++) {
                    const float e = diag ? __expf(sc[i] - m) : 0.f;
                    l += e;
                    pb[i] = (g & 1) ? pack_bf16(0.f, e) : pack_bf16(e, 0.f);
                }
#pragma unroll
                for (int o = 16; o; o >>= 1) l += __shfl_xor_sync(~0u, l, o);
            }
            float acc[12][4];
#pragma unroll
            for (int i = 0; i < 12; i++) acc[i][0] = acc[i][1] = acc[i][2] = acc[i][3] = 0.f;
            if (lane < 8) st_tag(p.s->pmb + (uint32_t)(pair * PBLK + G * DH + src * 8 + lane), (lane & 1) ? l : m, tag);
            if (lane == 0) red_add(p.s->fin + ((epoch & 1) * NATT + pair) * 32, 256);
            if (u == G - 1 && lane < NREP) red_add(p.s->rep + (((epoch & 1) * 4 + grp) * NREP + lane) * 7 * 32, 256);
            if (lane == 0 && u == G - 4) mbar_arrive(bar_late, 1);
            if (lane == 0 && u == U_SG) mbar_arrive(bar_sg, 1);
            if (lane == 0 && pair == pf) mbar_arrive(bar_own, 1);
#pragma unroll
            for (int i = 0; i < 2; i++) {
                const int t = T_KV + 4 * u + 2 + i, s = t & 15;
                mbar_wait(bar_full + s * 8, (t >> 4) & 1);
                const uint32_t base = sb + s * SLOT;
#pragma unroll
                for (int blk = 0; blk < 2; blk++) {
#pragma unroll
                    for (int st = 0; st < 12; st++) {
                        uint32_t a[4];
                        ldsm4t(a, base + voff[st & 3] + (st >> 2) * 128 + blk * 6144);
                        mma16816(acc[st], a, pb[i * 4 + blk * 2], pb[i * 4 + blk * 2 + 1]);
                    }
                }
                __syncwarp();
                if (lane == 0) mbar_arrive(bar_empty + s * 8, 6);
            }
            float* pk = p.s->pmb + (uint32_t)(pair * PBLK + hi * (G * 32) + src * 32 + pr * 16 + g);
#pragma unroll
            for (int seg = 0; seg < 3; seg++) {
                float e0[4], e1[4];
#pragma unroll
                for (int i = 0; i < 4; i++) {
                    e0[i] = acc[seg * 4 + i][0] + acc[seg * 4 + i][3];
                    e1[i] = acc[seg * 4 + i][2] + acc[seg * 4 + i][1];
                }
                e0[0] += __shfl_xor_sync(~0u, e0[1], 1);
                e0[2] += __shfl_xor_sync(~0u, e0[3], 1);
                e1[0] += __shfl_xor_sync(~0u, e1[1], 1);
                e1[2] += __shfl_xor_sync(~0u, e1[3], 1);
                e0[0] += __shfl_xor_sync(~0u, e0[2], 2);
                e1[0] += __shfl_xor_sync(~0u, e1[2], 2);
                st_tag(pk + seg * (2 * G * 32), e0[0], tag);
                st_tag(pk + seg * (2 * G * 32) + 8, e1[0], tag);
            }
            if (lane == 0) red_add(p.s->fin + ((epoch & 1) * NATT + pair) * 32, 1);
            if (u == G - 1 && lane < NREP) red_add(p.s->rep + (((epoch & 1) * 4 + grp) * NREP + lane) * 7 * 32, 1);
        }
        if (lane == 0 && uw == 0) mbar_arrive(bar_d0, 1);
        if (lane == 0) mbar_arrive(bar_done, 1);
    }
    if (late) {
        mbar_wait(bar_done, 0);
        const int w = warp - W_WO;
        const int bt = 2 * (tig & 1) + hi;
        __nv_bfloat16* dst = p.out + bt * D_ + 160 * j + 16 * w + ((g & 1) ? g + 7 : g);
        asm volatile("" : "+l"(dst));
        const uint32_t lin = r8 * 320 + (w >> 1) * 64;
        const uint32_t abase = sb + (T_TAIL & 15) * SLOT + lin + (((2 * (w & 1) + (mat & 1)) ^ ((lin >> 7) & 3)) << 4) + (mat >> 1) * 2560;
        const uint32_t wbar = bar_full + (T_TAIL & 15) * 8;
        const uint4* ob = reinterpret_cast<const uint4*>(smem + SM_O + (g & 3) * (O_PITCH * 2)) + tig;
        float acc[4][4];
#pragma unroll
        for (int i = 0; i < 4; i++) acc[i][0] = acc[i][1] = acc[i][2] = acc[i][3] = 0.f;
        uint32_t a[2 * NT_L][4];
        mbar_wait(bar_h, 0);
#pragma unroll
        for (int i = 0; i < NT_L; i++) {
            mbar_wait(wbar + i * 8, 0);
            ldsm4t(a[2 * i], abase + i * SLOT);
            ldsm4t(a[2 * i + 1], abase + i * SLOT + 5120);
        }
        mbar_wait(bar_o, 0);
#pragma unroll
        for (int i = 0; i < NT_L; i++) {
            const uint4 bw = ob[i * 4];
            mma16816(acc[(2 * i) & 3], a[2 * i], bw.x, bw.y);
            mma16816(acc[(2 * i + 1) & 3], a[2 * i + 1], bw.z, bw.w);
        }
#pragma unroll
        for (int e = 0; e < 4; e++) acc[2][e] = (acc[0][e] + acc[2][e]) + (acc[1][e] + acc[3][e]);
        const float lo = hi ? acc[2][1] : acc[2][0];
        const float up = hi ? acc[2][3] : acc[2][2];
        const float got = __shfl_xor_sync(~0u, (g & 1) ? lo : up, 4);
        out_red(dst, (g & 1) ? got : lo, (g & 1) ? up : got);
        return;
    }
    if (warp < W_S) return;
    }

    if (warp >= W_CMB) {
        const int f = (warp - W_CMB) * 128 + 4 * lane, b = f / DH, d = f - b * DH;
        const float* sp = p.s->amb + strip_role().rt * (12 * 4 * DH) + f;
        uint2* dp = reinterpret_cast<uint2*>(smem + SM_A + b * A_PITCH + (d >> 5) * 64 + ((d >> 2) & 3) * 16 + ((d >> 4) & 1) * 8);
        const bool swp = d & 8;
        mbar_wait(bar_sg, 0);
        uint4 v[NT_S];
        for (int it = 0; it < SPIN_LIMIT; it++) {
            uint32_t bad = 0;
#pragma unroll
            for (int i = 0; i < NT_S; i++) v[i] = ld_mb4(sp + i * (4 * DH));
#pragma unroll
            for (int i = 0; i < NT_S; i++) bad = chk(chk(chk(chk(bad, v[i].x, tag), v[i].y, tag), v[i].z, tag), v[i].w, tag);
            if (!__any_sync(~0u, bad & 1)) break;
            __nanosleep(100);
        }
#pragma unroll
        for (int i = 0; i < NT_S; i++) {
            const uint32_t x0 = __byte_perm(v[i].x, v[i].y, 0x7632), x1 = __byte_perm(v[i].z, v[i].w, 0x7632);
            dp[i * 48] = make_uint2(swp ? x1 : x0, swp ? x0 : x1);
        }
        __syncwarp();
        if (lane == 0) mbar_arrive(bar_a, 1);
    }
    {
        const int w = warp - W_S;
        const int mi = lane >> 3, t4 = (lane >> 1) & 3;
        const int row = 4 * t4 + (lane & 1) + 2 * ((t4 >> 1) ^ (mi >> 1));
        const uint32_t loff = row * 32 + (((mi & 1) ^ ((row >> 2) & 1)) << 4);
        __nv_bfloat16* dst = p.out + (2 * (mi & 1) + (mi >> 1)) * D_ + 16 * strip_role().cb + 2 * (lane & 7);
        asm volatile("" : "+l"(dst));
        mbar_wait(bar_h, 0);
        mbar_wait(bar_a, 0);
        constexpr int KS = 6;
        const int bx0 = w >> 1, s0 = (w & 1) * KS;
        uint2 af[12];
#pragma unroll
        for (int n = 0; n < 2; n++)
#pragma unroll
            for (int k = 0; k < KS; k++) {
                const int s = s0 + k;
                af[n * KS + k] = *reinterpret_cast<const uint2*>(smem + SM_A + (g & 3) * A_PITCH + (n * KS + bx0) * 384 + (s >> 1) * 64 + tig * 16 + (s & 1) * 8);
            }
        if (is_att) mbar_wait(bar_d0, 0);
#pragma unroll 1
        for (int blk = 0; blk < (is_att ? 1 : 2); blk++) {
            float acc[4][4];
#pragma unroll
            for (int i = 0; i < 4; i++) acc[i][0] = acc[i][1] = acc[i][2] = acc[i][3] = 0.f;
#pragma unroll
            for (int n = 0; n < 2; n++) {
                const int bx = n * KS + bx0, t = T_TAIL + bx;
                const uint32_t bar = is_att ? bar_full + (t & 15) * 8 : bar_full + (8 + 2 * blk + (bx >= 6)) * 8;
                const uint32_t box = (is_att ? sb + (t & 15) * SLOT : sb + (blk * 12 + bx) * BOX) + loff + s0 * 512;
                mbar_wait(bar, is_att ? (t >> 4) & 1 : 0);
#pragma unroll
                for (int k = 0; k < KS; k++) {
                    uint32_t a[4];
                    ldsm4t(a, box + k * 512);
                    mma16816(acc[(n * KS + k) & 3], a, af[n * KS + k].x, af[n * KS + k].y);
                }
            }
            float r0 = hi ? acc[0][2] : acc[0][0], r1 = hi ? acc[0][3] : acc[0][1];
#pragma unroll
            for (int i = 1; i < 4; i++) { r0 += hi ? acc[i][2] : acc[i][0]; r1 += hi ? acc[i][3] : acc[i][1]; }
            float* rb = reinterpret_cast<float*>(smem + SM_QB + blk * 3072);
            rb[w * 64 + (tig & 1) * 16 + hi * 8 + g] = r0;
            rb[w * 64 + (tig & 1) * 16 + hi * 8 + g + 32] = r1;
            asm volatile("bar.sync 5, 384;" ::: "memory");
            if (w == 11) {
                float2 r[12];
#pragma unroll
                for (int i = 0; i < 12; i++) r[i] = reinterpret_cast<const float2*>(rb)[i * 32 + lane];
#pragma unroll
                for (int st = 1; st < 12; st *= 2)
#pragma unroll
                    for (int i = 0; i + st < 12; i += 2 * st) { r[i].x += r[i + st].x; r[i].y += r[i + st].y; }
                out_red(dst + 16 * blk, r[0].x, r[0].y);
            }
        }
    }
}

typedef CUresult (*EncodeFn)(CUtensorMap*, CUtensorMapDataType, cuuint32_t, void*, const cuuint64_t*, const cuuint64_t*,
                             const cuuint32_t*, const cuuint32_t*, CUtensorMapInterleave, CUtensorMapSwizzle,
                             CUtensorMapL2promotion, CUtensorMapFloatOOBfill);

void make_map(EncodeFn fn, CUtensorMap* m, const void* ptr, int rows, int cols, int inner, int ncg, int nrows) {
    cuuint64_t dims[3] = {(cuuint64_t)inner, (cuuint64_t)(cols / inner), (cuuint64_t)rows};
    cuuint64_t strides[2] = {(cuuint64_t)inner * 2, (cuuint64_t)cols * 2};
    cuuint32_t box[3] = {(cuuint32_t)inner, (cuuint32_t)ncg, (cuuint32_t)nrows};
    cuuint32_t es[3] = {1, 1, 1};
    fn(m, CU_TENSOR_MAP_DATA_TYPE_BFLOAT16, 3, const_cast<void*>(ptr), dims, strides, box, es,
       CU_TENSOR_MAP_INTERLEAVE_NONE, inner == 64 ? CU_TENSOR_MAP_SWIZZLE_128B : CU_TENSOR_MAP_SWIZZLE_64B,
       CU_TENSOR_MAP_L2_PROMOTION_L2_128B, CU_TENSOR_MAP_FLOAT_OOB_FILL_NONE);
}

void make_strip_map(EncodeFn fn, CUtensorMap* m, const void* ptr, int rows) {
    cuuint64_t dims[2] = {(cuuint64_t)D_, (cuuint64_t)rows};
    cuuint64_t strides[1] = {(cuuint64_t)D_ * 2};
    cuuint32_t box[2] = {16, (cuuint32_t)DH};
    cuuint32_t es[2] = {1, 1};
    fn(m, CU_TENSOR_MAP_DATA_TYPE_BFLOAT16, 2, const_cast<void*>(ptr), dims, strides, box, es, CU_TENSOR_MAP_INTERLEAVE_NONE,
       CU_TENSOR_MAP_SWIZZLE_32B, CU_TENSOR_MAP_L2_PROMOTION_L2_128B, CU_TENSOR_MAP_FLOAT_OOB_FILL_NONE);
}

}

extern "C" void kernel_launch(void* const* d_in, const int* in_sizes, int n_in, void* d_out, int out_size) {
    (void)in_sizes; (void)n_in; (void)out_size;
    void* fnp = nullptr;
    cudaDriverEntryPointQueryResult qr;
    cudaGetDriverEntryPoint("cuTensorMapEncodeTiled", &fnp, cudaEnableDefault, &qr);
    EncodeFn fn = (EncodeFn)fnp;

    CUtensorMap m_wq, m_wo, m_w1, m_w3, m_wos, m_w2s;
    make_map(fn, &m_wq, d_in[3], 640, 6144, 64, 3, 32);
    make_map(fn, &m_wo, d_in[4], 6144, 640, 32, 5, 32);
    make_map(fn, &m_w1, d_in[6], 640, 1536, 64, 3, 16);
    make_map(fn, &m_w3, d_in[7], 640, 1536, 64, 3, 16);
    make_strip_map(fn, &m_wos, d_in[4], 6144);
    make_strip_map(fn, &m_w2s, d_in[8], 1536);

    Params p;
    p.x = (const __nv_bfloat16*)d_in[0];
    p.k = (const __nv_bfloat16*)d_in[1];
    p.v = (const __nv_bfloat16*)d_in[2];
    p.wq = (const __nv_bfloat16*)d_in[3];
    p.out = (__nv_bfloat16*)d_out;
    void* sp = nullptr;
    cudaGetSymbolAddress(&sp, g_s);
    p.s = (Scratch*)sp;

    cudaFuncSetAttribute(fused_decode_kernel, cudaFuncAttributeMaxDynamicSharedMemorySize, SM_TOTAL);
    fused_decode_kernel<<<NCTA, NTHREADS, SM_TOTAL>>>(p, m_wq, m_wo, m_w1, m_w3, m_wos, m_w2s);
}
```
